```python
import torch

def _softmax(x, axis=-1):
    return torch.softmax(x, dim=axis)
def _gelu(x):
    return torch.nn.functional.gelu(x, approximate="tanh")
def _silu(x):
    return torch.nn.functional.silu(x)
def _sigmoid(x):
    return torch.sigmoid(x)
def _layernorm(x, axis=-1, eps=1e-5):
    m = x.mean(dim=axis, keepdim=True)
    v = x.var(dim=axis, keepdim=True, unbiased=False)
    return (x - m) / torch.sqrt(v + eps)
def _scatter_add(tgt, idx, src, axis=0):
    return tgt.clone().index_add_(axis, idx, src)
def _segment_sum(src, seg, n):
    out = torch.zeros((n,) + src.shape[1:], dtype=src.dtype)
    return out.index_add_(0, seg, src)
def _pad(x, pw):
    flat = tuple(v for pair in reversed(pw) for v in pair)
    return torch.nn.functional.pad(x, flat)

kernel_name = 'interleave_layers__mha_block__softmax_full_mha__prompt'

def setup_inputs():

    _w = (lambda a: (lambda t: t.to(torch.bfloat16) if t.is_floating_point() else t)(torch.as_tensor(a)))
    def _A_setup():
        B, S, D, H = 1, 2048, 448, 16
        return {
            "x": _w((lambda *s: torch.randn(*s, dtype=torch.bfloat16) * 0.05)(B, S, D)),
            "wqkv": _w((lambda *s: torch.randn(*s, dtype=torch.bfloat16) * 0.05)(D, 3 * D)),
            "wo": _w((lambda *s: torch.randn(*s, dtype=torch.bfloat16) * 0.05)(D, D)),
        }
    _A_in = _A_setup()

    def _B_setup():
        B, S, D = 1, 2048, 448
        return {
            "x": _w((lambda *s: torch.randn(*s, dtype=torch.bfloat16) * 0.05)(B, S, D)),
            "wqkv": _w((lambda *s: torch.randn(*s, dtype=torch.bfloat16) * 0.1)(D, 3 * D)),
            "wo": _w((lambda *s: torch.randn(*s, dtype=torch.bfloat16) * 0.05)(D, D)),
        }
    _B_in = _B_setup()

    return {
        "A_x": _A_in["x"],
        "A_wqkv": _A_in["wqkv"],
        "A_wo": _A_in["wo"],
        "B_x": _B_in["x"],
        "B_wqkv": _B_in["wqkv"],
        "B_wo": _B_in["wo"],
    }

def reference(A_x, A_wqkv, A_wo, B_x, B_wqkv, B_wo):
    def _A_ref(x, wqkv, wo):
        B, S, D = x.shape
        H = 16
        Dh = D // H
        qkv = (lambda x, *d: x.permute(*d))((x @ wqkv).reshape(B, S, 3, H, Dh), 2, 0, 3, 1, 4)
        q, k, v = qkv[0], qkv[1], qkv[2]
        scores = torch.einsum("bhqd,bhkd->bhqk", q, k) * (Dh ** -0.5)
        p = _softmax(scores, axis=-1)
        o = torch.einsum("bhqk,bhkd->bhqd", p, v)
        return (lambda x, *d: x.permute(*d))(o, 0, 2, 1, 3).reshape(B, S, D) @ wo

    def _B_ref(x, wqkv, wo):
        B, S, D = x.shape
        H = 16; Dh = D // H
        qkv = (lambda x, *d: x.permute(*d))((x @ wqkv).reshape(B, S, 3, H, Dh), 2, 0, 3, 1, 4)
        q, k, v = qkv[0], qkv[1], qkv[2]
        scale = Dh ** -0.5
        scores = torch.einsum("bhqd,bhkd->bhqk", q, k) * scale
        p = _softmax(scores, axis=-1)
        o = torch.einsum("bhqk,bhkd->bhqd", p, v)
        return (lambda x, *d: x.permute(*d))(o, 0, 2, 1, 3).reshape(B, S, D) @ wo

    x = A_x
    x = x + _A_ref(_layernorm(x, axis=-1), A_wqkv, A_wo)
    x = x + _B_ref(_layernorm(x, axis=-1), B_wqkv, B_wo)
    x = x + _A_ref(_layernorm(x, axis=-1), A_wqkv, A_wo)
    x = x + _B_ref(_layernorm(x, axis=-1), B_wqkv, B_wo)
    return x
```

```cpp
#include <cuda_runtime.h>
#include <cuda_bf16.h>
#include <cuda.h>
#include <stdint.h>

#define NL 4
#define NPOLY 10

namespace {

constexpr int S_LEN = 2048, DM = 448, NH = 16, DH = 28;

__device__ uint4 g_xf[2][32][28][128];
__device__ uint4 g_of[2][32][32][128];
__device__ uint4 g_st[2][S_LEN][8];
__device__ __align__(16) uint32_t g_csp[NH][8][200];
__device__ __align__(1024) uint8_t g_kv[2][NH][8][32768];
__device__ uint4 g_kn[2][NH][32];
__device__ __align__(128) unsigned g_kvready[4][NH][32];

constexpr int SM_W2 = 0;
constexpr int SM_W1 = 57344;
constexpr int SM_RING = 143360;
constexpr int SM_TMP = 225280;
constexpr int SM_MISC = 229376;
constexpr int SM_BAR = SM_MISC;
constexpr int SM_CS = SM_MISC + 256;
constexpr int SM_NORM = SM_CS + 768;
constexpr int SM_DEC = SM_NORM + 64;
constexpr int SM_TOTAL = SM_DEC + 64;
static_assert(SM_TOTAL <= 232448, "smem");
constexpr int B_W1 = 0, B_W2 = 2, B_P1DONE = 3, B_P3DONE = 4, B_DEC = 5;
constexpr int B_FULL = 6;
constexpr int B_ADONE = 11;
constexpr int B_EMPTY = 16;
constexpr int B_KVPUB = 21;
constexpr int B_OWN = 22;
constexpr int B_CS = 24;
__device__ __forceinline__ uint32_t stage_par(int u, uint32_t pass) { return ((u / 5) ^ (u % 5 ? pass : 0u)) & 1; }

__device__ __forceinline__ void wgmma_n64_rs_a(float (&d)[32], uint32_t a0, uint32_t a1, uint32_t a2, uint32_t a3, uint64_t descB) {
    asm volatile("wgmma.mma_async.sync.aligned.m64n64k16.f32.bf16.bf16 {%0, %1, %2, %3, %4, %5, %6, %7, %8, %9, %10, %11, %12, %13, %14, %15, %16, %17, %18, %19, %20, %21, %22, %23, %24, %25, %26, %27, %28, %29, %30, %31}, {%32,%33,%34,%35}, %36, 1, 1, 1, 0;"
        : "+f"(d[0]), "+f"(d[1]), "+f"(d[2]), "+f"(d[3]), "+f"(d[4]), "+f"(d[5]), "+f"(d[6]), "+f"(d[7]), "+f"(d[8]), "+f"(d[9]), "+f"(d[10]), "+f"(d[11]), "+f"(d[12]), "+f"(d[13]), "+f"(d[14]), "+f"(d[15]), "+f"(d[16]), "+f"(d[17]), "+f"(d[18]), "+f"(d[19]), "+f"(d[20]), "+f"(d[21]), "+f"(d[22]), "+f"(d[23]), "+f"(d[24]), "+f"(d[25]), "+f"(d[26]), "+f"(d[27]), "+f"(d[28]), "+f"(d[29]), "+f"(d[30]), "+f"(d[31])
        : "r"(a0), "r"(a1), "r"(a2), "r"(a3), "l"(descB));
}
__device__ __forceinline__ void wgmma_n64_rs_z(float (&d)[32], uint32_t a0, uint32_t a1, uint32_t a2, uint32_t a3, uint64_t descB) {
    asm volatile("wgmma.mma_async.sync.aligned.m64n64k16.f32.bf16.bf16 {%0, %1, %2, %3, %4, %5, %6, %7, %8, %9, %10, %11, %12, %13, %14, %15, %16, %17, %18, %19, %20, %21, %22, %23, %24, %25, %26, %27, %28, %29, %30, %31}, {%32,%33,%34,%35}, %36, 0, 1, 1, 0;"
        : "=f"(d[0]), "=f"(d[1]), "=f"(d[2]), "=f"(d[3]), "=f"(d[4]), "=f"(d[5]), "=f"(d[6]), "=f"(d[7]), "=f"(d[8]), "=f"(d[9]), "=f"(d[10]), "=f"(d[11]), "=f"(d[12]), "=f"(d[13]), "=f"(d[14]), "=f"(d[15]), "=f"(d[16]), "=f"(d[17]), "=f"(d[18]), "=f"(d[19]), "=f"(d[20]), "=f"(d[21]), "=f"(d[22]), "=f"(d[23]), "=f"(d[24]), "=f"(d[25]), "=f"(d[26]), "=f"(d[27]), "=f"(d[28]), "=f"(d[29]), "=f"(d[30]), "=f"(d[31])
        : "r"(a0), "r"(a1), "r"(a2), "r"(a3), "l"(descB));
}
__device__ __forceinline__ void wgmma_n32t_rs_a(float (&d)[16], uint32_t a0, uint32_t a1, uint32_t a2, uint32_t a3, uint64_t descB) {
    asm volatile("wgmma.mma_async.sync.aligned.m64n32k16.f32.bf16.bf16 {%0, %1, %2, %3, %4, %5, %6, %7, %8, %9, %10, %11, %12, %13, %14, %15}, {%16,%17,%18,%19}, %20, 1, 1, 1, 1;"
        : "+f"(d[0]), "+f"(d[1]), "+f"(d[2]), "+f"(d[3]), "+f"(d[4]), "+f"(d[5]), "+f"(d[6]), "+f"(d[7]), "+f"(d[8]), "+f"(d[9]), "+f"(d[10]), "+f"(d[11]), "+f"(d[12]), "+f"(d[13]), "+f"(d[14]), "+f"(d[15])
        : "r"(a0), "r"(a1), "r"(a2), "r"(a3), "l"(descB));
}
__device__ __forceinline__ void wgmma_n96t_rs_a(float (&d)[48], uint32_t a0, uint32_t a1, uint32_t a2, uint32_t a3, uint64_t descB) {
    asm volatile("wgmma.mma_async.sync.aligned.m64n96k16.f32.bf16.bf16 {%0, %1, %2, %3, %4, %5, %6, %7, %8, %9, %10, %11, %12, %13, %14, %15, %16, %17, %18, %19, %20, %21, %22, %23, %24, %25, %26, %27, %28, %29, %30, %31, %32, %33, %34, %35, %36, %37, %38, %39, %40, %41, %42, %43, %44, %45, %46, %47}, {%48,%49,%50,%51}, %52, 1, 1, 1, 1;"
        : "+f"(d[0]), "+f"(d[1]), "+f"(d[2]), "+f"(d[3]), "+f"(d[4]), "+f"(d[5]), "+f"(d[6]), "+f"(d[7]), "+f"(d[8]), "+f"(d[9]), "+f"(d[10]), "+f"(d[11]), "+f"(d[12]), "+f"(d[13]), "+f"(d[14]), "+f"(d[15]), "+f"(d[16]), "+f"(d[17]), "+f"(d[18]), "+f"(d[19]), "+f"(d[20]), "+f"(d[21]), "+f"(d[22]), "+f"(d[23]), "+f"(d[24]), "+f"(d[25]), "+f"(d[26]), "+f"(d[27]), "+f"(d[28]), "+f"(d[29]), "+f"(d[30]), "+f"(d[31]), "+f"(d[32]), "+f"(d[33]), "+f"(d[34]), "+f"(d[35]), "+f"(d[36]), "+f"(d[37]), "+f"(d[38]), "+f"(d[39]), "+f"(d[40]), "+f"(d[41]), "+f"(d[42]), "+f"(d[43]), "+f"(d[44]), "+f"(d[45]), "+f"(d[46]), "+f"(d[47])
        : "r"(a0), "r"(a1), "r"(a2), "r"(a3), "l"(descB));
}
__device__ __forceinline__ void wgmma_n96t_rs_z(float (&d)[48], uint32_t a0, uint32_t a1, uint32_t a2, uint32_t a3, uint64_t descB) {
    asm volatile("wgmma.mma_async.sync.aligned.m64n96k16.f32.bf16.bf16 {%0, %1, %2, %3, %4, %5, %6, %7, %8, %9, %10, %11, %12, %13, %14, %15, %16, %17, %18, %19, %20, %21, %22, %23, %24, %25, %26, %27, %28, %29, %30, %31, %32, %33, %34, %35, %36, %37, %38, %39, %40, %41, %42, %43, %44, %45, %46, %47}, {%48,%49,%50,%51}, %52, 0, 1, 1, 1;"
        : "=f"(d[0]), "=f"(d[1]), "=f"(d[2]), "=f"(d[3]), "=f"(d[4]), "=f"(d[5]), "=f"(d[6]), "=f"(d[7]), "=f"(d[8]), "=f"(d[9]), "=f"(d[10]), "=f"(d[11]), "=f"(d[12]), "=f"(d[13]), "=f"(d[14]), "=f"(d[15]), "=f"(d[16]), "=f"(d[17]), "=f"(d[18]), "=f"(d[19]), "=f"(d[20]), "=f"(d[21]), "=f"(d[22]), "=f"(d[23]), "=f"(d[24]), "=f"(d[25]), "=f"(d[26]), "=f"(d[27]), "=f"(d[28]), "=f"(d[29]), "=f"(d[30]), "=f"(d[31]), "=f"(d[32]), "=f"(d[33]), "=f"(d[34]), "=f"(d[35]), "=f"(d[36]), "=f"(d[37]), "=f"(d[38]), "=f"(d[39]), "=f"(d[40]), "=f"(d[41]), "=f"(d[42]), "=f"(d[43]), "=f"(d[44]), "=f"(d[45]), "=f"(d[46]), "=f"(d[47])
        : "r"(a0), "r"(a1), "r"(a2), "r"(a3), "l"(descB));
}
__device__ __forceinline__ void wgmma_n64t_rs_a(float (&d)[32], uint32_t a0, uint32_t a1, uint32_t a2, uint32_t a3, uint64_t descB) {
    asm volatile("wgmma.mma_async.sync.aligned.m64n64k16.f32.bf16.bf16 {%0, %1, %2, %3, %4, %5, %6, %7, %8, %9, %10, %11, %12, %13, %14, %15, %16, %17, %18, %19, %20, %21, %22, %23, %24, %25, %26, %27, %28, %29, %30, %31}, {%32,%33,%34,%35}, %36, 1, 1, 1, 1;"
        : "+f"(d[0]), "+f"(d[1]), "+f"(d[2]), "+f"(d[3]), "+f"(d[4]), "+f"(d[5]), "+f"(d[6]), "+f"(d[7]), "+f"(d[8]), "+f"(d[9]), "+f"(d[10]), "+f"(d[11]), "+f"(d[12]), "+f"(d[13]), "+f"(d[14]), "+f"(d[15]), "+f"(d[16]), "+f"(d[17]), "+f"(d[18]), "+f"(d[19]), "+f"(d[20]), "+f"(d[21]), "+f"(d[22]), "+f"(d[23]), "+f"(d[24]), "+f"(d[25]), "+f"(d[26]), "+f"(d[27]), "+f"(d[28]), "+f"(d[29]), "+f"(d[30]), "+f"(d[31])
        : "r"(a0), "r"(a1), "r"(a2), "r"(a3), "l"(descB));
}
__device__ __forceinline__ void wgmma_n64t_rs_z(float (&d)[32], uint32_t a0, uint32_t a1, uint32_t a2, uint32_t a3, uint64_t descB) {
    asm volatile("wgmma.mma_async.sync.aligned.m64n64k16.f32.bf16.bf16 {%0, %1, %2, %3, %4, %5, %6, %7, %8, %9, %10, %11, %12, %13, %14, %15, %16, %17, %18, %19, %20, %21, %22, %23, %24, %25, %26, %27, %28, %29, %30, %31}, {%32,%33,%34,%35}, %36, 0, 1, 1, 1;"
        : "=f"(d[0]), "=f"(d[1]), "=f"(d[2]), "=f"(d[3]), "=f"(d[4]), "=f"(d[5]), "=f"(d[6]), "=f"(d[7]), "=f"(d[8]), "=f"(d[9]), "=f"(d[10]), "=f"(d[11]), "=f"(d[12]), "=f"(d[13]), "=f"(d[14]), "=f"(d[15]), "=f"(d[16]), "=f"(d[17]), "=f"(d[18]), "=f"(d[19]), "=f"(d[20]), "=f"(d[21]), "=f"(d[22]), "=f"(d[23]), "=f"(d[24]), "=f"(d[25]), "=f"(d[26]), "=f"(d[27]), "=f"(d[28]), "=f"(d[29]), "=f"(d[30]), "=f"(d[31])
        : "r"(a0), "r"(a1), "r"(a2), "r"(a3), "l"(descB));
}
__device__ __forceinline__ void ll_fetch4(uint32_t* a, const void* p) {
    asm volatile("{\n.reg .pred p;\n.reg .u32 m, n;\nmov.u32 n, 0;\nbar.warp.sync 0xffffffff;\nGET_%=:\n"
        "ld.relaxed.gpu.global.v4.u32 {%0,%1,%2,%3}, [%16+0];\n"
        "ld.relaxed.gpu.global.v4.u32 {%4,%5,%6,%7}, [%16+2048];\n"
        "ld.relaxed.gpu.global.v4.u32 {%8,%9,%10,%11}, [%16+4096];\n"
        "ld.relaxed.gpu.global.v4.u32 {%12,%13,%14,%15}, [%16+6144];\n"
        "min.u32 m, %0, %1;\nmin.u32 m, m, %2;\nmin.u32 m, m, %3;\nmin.u32 m, m, %4;\nmin.u32 m, m, %5;\nmin.u32 m, m, %6;\nmin.u32 m, m, %7;\nmin.u32 m, m, %8;\nmin.u32 m, m, %9;\nmin.u32 m, m, %10;\nmin.u32 m, m, %11;\nmin.u32 m, m, %12;\nmin.u32 m, m, %13;\nmin.u32 m, m, %14;\nmin.u32 m, m, %15;\n"
        "setp.eq.u32 p, m, 0;\nvote.sync.any.pred p, p, 0xffffffff;\n@!p bra DONE_%=;\n"
        "add.u32 n, n, 1;\nsetp.lt.u32 p, n, 4194304;\n@p bra GET_%=;\ntrap;\nDONE_%=:\n}\n"
        : "=r"(a[0]), "=r"(a[1]), "=r"(a[2]), "=r"(a[3]), "=r"(a[4]), "=r"(a[5]), "=r"(a[6]), "=r"(a[7]), "=r"(a[8]), "=r"(a[9]), "=r"(a[10]), "=r"(a[11]), "=r"(a[12]), "=r"(a[13]), "=r"(a[14]), "=r"(a[15]) : "l"(p) : "memory");
}
__device__ __forceinline__ void ll_fetch8(uint32_t* a, const void* p) {
    asm volatile("{\n.reg .pred p;\n.reg .u32 m, n;\nmov.u32 n, 0;\nbar.warp.sync 0xffffffff;\nGET_%=:\n"
        "ld.relaxed.gpu.global.v4.u32 {%0,%1,%2,%3}, [%32+0];\n"
        "ld.relaxed.gpu.global.v4.u32 {%4,%5,%6,%7}, [%32+2048];\n"
        "ld.relaxed.gpu.global.v4.u32 {%8,%9,%10,%11}, [%32+4096];\n"
        "ld.relaxed.gpu.global.v4.u32 {%12,%13,%14,%15}, [%32+6144];\n"
        "ld.relaxed.gpu.global.v4.u32 {%16,%17,%18,%19}, [%32+8192];\n"
        "ld.relaxed.gpu.global.v4.u32 {%20,%21,%22,%23}, [%32+10240];\n"
        "ld.relaxed.gpu.global.v4.u32 {%24,%25,%26,%27}, [%32+12288];\n"
        "ld.relaxed.gpu.global.v4.u32 {%28,%29,%30,%31}, [%32+14336];\n"
        "min.u32 m, %0, %1;\nmin.u32 m, m, %2;\nmin.u32 m, m, %3;\nmin.u32 m, m, %4;\nmin.u32 m, m, %5;\nmin.u32 m, m, %6;\nmin.u32 m, m, %7;\nmin.u32 m, m, %8;\nmin.u32 m, m, %9;\nmin.u32 m, m, %10;\nmin.u32 m, m, %11;\nmin.u32 m, m, %12;\nmin.u32 m, m, %13;\nmin.u32 m, m, %14;\nmin.u32 m, m, %15;\nmin.u32 m, m, %16;\nmin.u32 m, m, %17;\nmin.u32 m, m, %18;\nmin.u32 m, m, %19;\nmin.u32 m, m, %20;\nmin.u32 m, m, %21;\nmin.u32 m, m, %22;\nmin.u32 m, m, %23;\nmin.u32 m, m, %24;\nmin.u32 m, m, %25;\nmin.u32 m, m, %26;\nmin.u32 m, m, %27;\nmin.u32 m, m, %28;\nmin.u32 m, m, %29;\nmin.u32 m, m, %30;\nmin.u32 m, m, %31;\n"
        "setp.eq.u32 p, m, 0;\nvote.sync.any.pred p, p, 0xffffffff;\n@!p bra DONE_%=;\n"
        "add.u32 n, n, 1;\nsetp.lt.u32 p, n, 4194304;\n@p bra GET_%=;\ntrap;\nDONE_%=:\n}\n"
        : "=r"(a[0]), "=r"(a[1]), "=r"(a[2]), "=r"(a[3]), "=r"(a[4]), "=r"(a[5]), "=r"(a[6]), "=r"(a[7]), "=r"(a[8]), "=r"(a[9]), "=r"(a[10]), "=r"(a[11]), "=r"(a[12]), "=r"(a[13]), "=r"(a[14]), "=r"(a[15]), "=r"(a[16]), "=r"(a[17]), "=r"(a[18]), "=r"(a[19]), "=r"(a[20]), "=r"(a[21]), "=r"(a[22]), "=r"(a[23]), "=r"(a[24]), "=r"(a[25]), "=r"(a[26]), "=r"(a[27]), "=r"(a[28]), "=r"(a[29]), "=r"(a[30]), "=r"(a[31]) : "l"(p) : "memory");
}
template <int PENDING> __device__ __forceinline__ void ll_lds4(uint32_t* a, uint32_t s, const void* p) {
    asm volatile("{\n.reg .pred p;\n.reg .u32 m, n;\nmov.u32 n, 0;\ncp.async.wait_group %18;\nbar.warp.sync 0xffffffff;\nGET_%=:\n"
        "ld.shared.v4.u32 {%0,%1,%2,%3}, [%16+0];\n"
        "ld.shared.v4.u32 {%4,%5,%6,%7}, [%16+2048];\n"
        "ld.shared.v4.u32 {%8,%9,%10,%11}, [%16+4096];\n"
        "ld.shared.v4.u32 {%12,%13,%14,%15}, [%16+6144];\n"
        "min.u32 m, %0, %1;\nmin.u32 m, m, %2;\nmin.u32 m, m, %3;\nmin.u32 m, m, %4;\nmin.u32 m, m, %5;\nmin.u32 m, m, %6;\nmin.u32 m, m, %7;\nmin.u32 m, m, %8;\nmin.u32 m, m, %9;\nmin.u32 m, m, %10;\nmin.u32 m, m, %11;\nmin.u32 m, m, %12;\nmin.u32 m, m, %13;\nmin.u32 m, m, %14;\nmin.u32 m, m, %15;\n"
        "setp.eq.u32 p, m, 0;\nvote.sync.any.pred p, p, 0xffffffff;\n@!p bra DONE_%=;\n"
        "cp.async.cg.shared.global [%16+0], [%17+0], 16;\n"
        "cp.async.cg.shared.global [%16+2048], [%17+2048], 16;\n"
        "cp.async.cg.shared.global [%16+4096], [%17+4096], 16;\n"
        "cp.async.cg.shared.global [%16+6144], [%17+6144], 16;\n"
        "cp.async.wait_all;\nadd.u32 n, n, 1;\nsetp.lt.u32 p, n, 4194304;\n@p bra GET_%=;\ntrap;\nDONE_%=:\n}\n"
        : "=r"(a[0]), "=r"(a[1]), "=r"(a[2]), "=r"(a[3]), "=r"(a[4]), "=r"(a[5]), "=r"(a[6]), "=r"(a[7]), "=r"(a[8]), "=r"(a[9]), "=r"(a[10]), "=r"(a[11]), "=r"(a[12]), "=r"(a[13]), "=r"(a[14]), "=r"(a[15]) : "r"(s), "l"(p), "n"(PENDING) : "memory");
}
template <int PENDING> __device__ __forceinline__ void ll_lds4w(uint32_t* a, uint32_t s, const void* p) {
    asm volatile("{\n.reg .pred p;\n.reg .u32 m, n;\nmov.u32 n, 0;\ncp.async.wait_group %18;\nbar.warp.sync 0xffffffff;\nGET_%=:\n"
        "ld.shared.v4.u32 {%0,%1,%2,%3}, [%16+0];\n"
        "ld.shared.v4.u32 {%4,%5,%6,%7}, [%16+512];\n"
        "ld.shared.v4.u32 {%8,%9,%10,%11}, [%16+4096];\n"
        "ld.shared.v4.u32 {%12,%13,%14,%15}, [%16+4608];\n"
        "min.u32 m, %0, %1;\nmin.u32 m, m, %2;\nmin.u32 m, m, %3;\nmin.u32 m, m, %4;\nmin.u32 m, m, %5;\nmin.u32 m, m, %6;\nmin.u32 m, m, %7;\nmin.u32 m, m, %8;\nmin.u32 m, m, %9;\nmin.u32 m, m, %10;\nmin.u32 m, m, %11;\nmin.u32 m, m, %12;\nmin.u32 m, m, %13;\nmin.u32 m, m, %14;\nmin.u32 m, m, %15;\n"
        "setp.eq.u32 p, m, 0;\nvote.sync.any.pred p, p, 0xffffffff;\n@!p bra DONE_%=;\n"
        "cp.async.cg.shared.global [%16+0], [%17+0], 16;\n"
        "cp.async.cg.shared.global [%16+512], [%17+2048], 16;\n"
        "cp.async.cg.shared.global [%16+4096], [%17+4096], 16;\n"
        "cp.async.cg.shared.global [%16+4608], [%17+6144], 16;\n"
        "cp.async.wait_all;\nadd.u32 n, n, 1;\nsetp.lt.u32 p, n, 4194304;\n@p bra GET_%=;\ntrap;\nDONE_%=:\n}\n"
        : "=r"(a[0]), "=r"(a[1]), "=r"(a[2]), "=r"(a[3]), "=r"(a[4]), "=r"(a[5]), "=r"(a[6]), "=r"(a[7]), "=r"(a[8]), "=r"(a[9]), "=r"(a[10]), "=r"(a[11]), "=r"(a[12]), "=r"(a[13]), "=r"(a[14]), "=r"(a[15]) : "r"(s), "l"(p), "n"(PENDING) : "memory");
}
__device__ __forceinline__ void ll_settle4(uint32_t* a, const void* p) {
    asm volatile("{\n.reg .pred p;\n.reg .u32 m, n;\nmov.u32 n, 0;\nCHK_%=:\n"
        "min.u32 m, %0, %1;\nmin.u32 m, m, %2;\nmin.u32 m, m, %3;\nmin.u32 m, m, %4;\nmin.u32 m, m, %5;\nmin.u32 m, m, %6;\nmin.u32 m, m, %7;\nmin.u32 m, m, %8;\nmin.u32 m, m, %9;\nmin.u32 m, m, %10;\nmin.u32 m, m, %11;\nmin.u32 m, m, %12;\nmin.u32 m, m, %13;\nmin.u32 m, m, %14;\nmin.u32 m, m, %15;\n"
        "setp.eq.u32 p, m, 0;\nvote.sync.any.pred p, p, 0xffffffff;\n@!p bra DONE_%=;\n"
        "ld.relaxed.gpu.global.v4.u32 {%0,%1,%2,%3}, [%16+0];\n"
        "ld.relaxed.gpu.global.v4.u32 {%4,%5,%6,%7}, [%16+2048];\n"
        "ld.relaxed.gpu.global.v4.u32 {%8,%9,%10,%11}, [%16+4096];\n"
        "ld.relaxed.gpu.global.v4.u32 {%12,%13,%14,%15}, [%16+6144];\n"
        "add.u32 n, n, 1;\nsetp.lt.u32 p, n, 4194304;\n@p bra CHK_%=;\ntrap;\nDONE_%=:\n}\n"
        : "+r"(a[0]), "+r"(a[1]), "+r"(a[2]), "+r"(a[3]), "+r"(a[4]), "+r"(a[5]), "+r"(a[6]), "+r"(a[7]), "+r"(a[8]), "+r"(a[9]), "+r"(a[10]), "+r"(a[11]), "+r"(a[12]), "+r"(a[13]), "+r"(a[14]), "+r"(a[15]) : "l"(p) : "memory");
}
__device__ __forceinline__ void ll_settle_stats(uint32_t* a, const void* p) {
    asm volatile("{\n.reg .pred p;\n.reg .u32 m, n;\nmov.u32 n, 0;\nCHK_%=:\n"
        "min.u32 m, %0, %1;\nmin.u32 m, m, %2;\nmin.u32 m, m, %3;\nmin.u32 m, m, %4;\nmin.u32 m, m, %5;\nmin.u32 m, m, %6;\nmin.u32 m, m, %7;\nmin.u32 m, m, %8;\nmin.u32 m, m, %9;\nmin.u32 m, m, %10;\nmin.u32 m, m, %11;\nmin.u32 m, m, %12;\nmin.u32 m, m, %13;\nmin.u32 m, m, %14;\nmin.u32 m, m, %15;\n"
        "setp.eq.u32 p, m, 0;\nvote.sync.any.pred p, p, 0xffffffff;\n@!p bra DONE_%=;\n"
        "ld.relaxed.gpu.global.v4.u32 {%0,%1,%2,%3}, [%16+0];\n"
        "ld.relaxed.gpu.global.v4.u32 {%4,%5,%6,%7}, [%16+16];\n"
        "ld.relaxed.gpu.global.v4.u32 {%8,%9,%10,%11}, [%16+1024];\n"
        "ld.relaxed.gpu.global.v4.u32 {%12,%13,%14,%15}, [%16+1040];\n"
        "add.u32 n, n, 1;\nsetp.lt.u32 p, n, 4194304;\n@p bra CHK_%=;\ntrap;\nDONE_%=:\n}\n"
        : "+r"(a[0]), "+r"(a[1]), "+r"(a[2]), "+r"(a[3]), "+r"(a[4]), "+r"(a[5]), "+r"(a[6]), "+r"(a[7]), "+r"(a[8]), "+r"(a[9]), "+r"(a[10]), "+r"(a[11]), "+r"(a[12]), "+r"(a[13]), "+r"(a[14]), "+r"(a[15]) : "l"(p) : "memory");
}

__device__ __forceinline__ void wg_fence() { asm volatile("wgmma.fence.sync.aligned;" ::: "memory"); }
__device__ __forceinline__ void wg_commit() { asm volatile("wgmma.commit_group.sync.aligned;" ::: "memory"); }
template <int N> __device__ __forceinline__ void wg_wait() { asm volatile("wgmma.wait_group.sync.aligned %0;" ::"n"(N) : "memory"); }
__host__ __device__ constexpr uint64_t mkdesc(uint32_t addr, uint32_t lbo, uint32_t sbo, uint32_t swz) {
    return (uint64_t)((addr & 0x3FFFF) >> 4) | ((uint64_t)(lbo >> 4) << 16) | ((uint64_t)(sbo >> 4) << 32) | ((uint64_t)swz << 62);
}
__device__ __forceinline__ void mbar_init(uint32_t bar, int cnt) { asm volatile("mbarrier.init.shared::cta.b64 [%0], %1;" ::"r"(bar), "r"(cnt)); }
__device__ __forceinline__ void mbar_arrive(uint32_t bar) { asm volatile("mbarrier.arrive.shared::cta.b64 _, [%0];" ::"r"(bar) : "memory"); }
__device__ __forceinline__ void mbar_expect_tx(uint32_t bar, uint32_t bytes) { asm volatile("mbarrier.arrive.expect_tx.shared::cta.b64 _, [%0], %1;" ::"r"(bar), "r"(bytes) : "memory"); }
__device__ __forceinline__ void mbar_wait(uint32_t bar, uint32_t parity) {
    asm volatile(
        "{\n.reg .pred p;\n.reg .u32 n;\nmov.u32 n, 0;\n"
        "WAIT_%=:\nmbarrier.try_wait.parity.shared::cta.b64 p, [%0], %1;\n@p bra DONE_%=;\n"
        "add.u32 n, n, 1;\nsetp.lt.u32 p, n, 2097152;\n@p bra WAIT_%=;\ntrap;\nDONE_%=:\n}\n" ::"r"(bar), "r"(parity) : "memory");
}
__device__ __forceinline__ uint32_t mbar_test(uint32_t bar, uint32_t parity) {
    uint32_t ok;
    asm volatile("{\n.reg .pred p;\nmbarrier.test_wait.parity.shared::cta.b64 p, [%1], %2;\nselp.u32 %0, 1, 0, p;\n}\n" : "=r"(ok) : "r"(bar), "r"(parity) : "memory");
    return ok;
}
__device__ __forceinline__ void bulk_g2s(uint32_t dst, const void* src, uint32_t bytes, uint32_t bar) {
    asm volatile("cp.async.bulk.shared::cluster.global.mbarrier::complete_tx::bytes [%0], [%1], %2, [%3];" ::"r"(dst), "l"(src), "r"(bytes), "r"(bar) : "memory");
}
__device__ __forceinline__ void bulk_s2g(void* dst, uint32_t src, uint32_t bytes) {
    asm volatile("cp.async.bulk.global.shared::cta.bulk_group [%0], [%1], %2;\ncp.async.bulk.commit_group;" ::"l"(dst), "r"(src), "r"(bytes) : "memory");
}
__device__ __forceinline__ void tma2d(uint32_t dst, const CUtensorMap* tm, int c0, int c1, uint32_t bar) {
    asm volatile("cp.async.bulk.tensor.2d.shared::cluster.global.mbarrier::complete_tx::bytes [%0], [%1, {%3, %4}], [%2];" ::"r"(dst), "l"(tm), "r"(bar), "r"(c0), "r"(c1) : "memory");
}
__device__ __forceinline__ void fence_async_smem() { asm volatile("fence.proxy.async.shared::cta;" ::: "memory"); }
__device__ __forceinline__ void fence_async_gmem() { asm volatile("fence.proxy.async.global;" ::: "memory"); }
__device__ __forceinline__ void bar_sync(int id, int n) { asm volatile("bar.sync %0, %1;" ::"r"(id), "r"(n) : "memory"); }
__device__ __forceinline__ void st_flag(unsigned* p, unsigned v) { asm volatile("st.relaxed.gpu.global.u32 [%0], %1;" ::"l"(p), "r"(v) : "memory"); }
__device__ __forceinline__ void poll_nz(const void* p) {
    asm volatile(
        "{\n.reg .pred p;\n.reg .u32 n, v;\nmov.u32 n, 0;\nbar.warp.sync 0xffffffff;\n"
        "POLL_%=:\nld.relaxed.gpu.global.u32 v, [%0];\nsetp.eq.u32 p, v, 0;\nvote.sync.any.pred p, p, 0xffffffff;\n@!p bra DONE_%=;\n"
        "add.u32 n, n, 1;\nsetp.lt.u32 p, n, 4194304;\n@p bra POLL_%=;\ntrap;\nDONE_%=:\n}\n" ::"l"(p) : "memory");
}
__device__ __forceinline__ void lds_wait_ge(uint32_t addr, int want) {
    asm volatile(
        "{\n.reg .pred p;\n.reg .u32 n, v;\nmov.u32 n, 0;\n"
        "SPIN_%=:\nld.volatile.shared.u32 v, [%0];\nsetp.ge.s32 p, v, %1;\n@p bra DONE_%=;\n"
        "nanosleep.u32 600;\nadd.u32 n, n, 1;\nsetp.lt.u32 p, n, 4194304;\n@p bra SPIN_%=;\ntrap;\nDONE_%=:\n}\n" ::"r"(addr), "r"(want) : "memory");
}
__device__ __forceinline__ void ld_ll(uint32_t* d, const void* p) {
    asm volatile("ld.relaxed.gpu.global.v4.u32 {%0,%1,%2,%3}, [%4];" : "=r"(d[0]), "=r"(d[1]), "=r"(d[2]), "=r"(d[3]) : "l"(p) : "memory");
}
__device__ __forceinline__ void st_ll(void* p, uint32_t a, uint32_t b, uint32_t c, uint32_t d) {
    asm volatile("st.relaxed.gpu.global.v4.u32 [%0], {%1,%2,%3,%4};" ::"l"(p), "r"(a), "r"(b), "r"(c), "r"(d) : "memory");
}
__device__ __forceinline__ uint32_t nz(uint32_t w) { return max(w, 1u); }
__device__ __forceinline__ float ex2(float x) { float y; asm("ex2.approx.ftz.f32 %0, %1;" : "=f"(y) : "f"(x)); return y; }
__device__ __forceinline__ uint32_t pack_bf16(float lo, float hi) { uint32_t r; asm("cvt.rn.bf16x2.f32 %0, %1, %2;" : "=r"(r) : "f"(hi), "f"(lo)); return r; }
__device__ __forceinline__ float bf_lo(uint32_t v) { return __uint_as_float(v << 16); }
__device__ __forceinline__ float bf_hi(uint32_t v) { return __uint_as_float(v & 0xFFFF0000u); }
__device__ __forceinline__ uint32_t bfma2(uint32_t a, uint32_t b, uint32_t c) { uint32_t d; asm("fma.rn.bf16x2 %0, %1, %2, %3;" : "=r"(d) : "r"(a), "r"(b), "r"(c)); return d; }
__device__ __forceinline__ uint32_t lop_andor(uint32_t a, uint32_t m, uint32_t o) { uint32_t d; asm("lop3.b32 %0, %1, %2, %3, 0xEA;" : "=r"(d) : "r"(a), "r"(m), "r"(o)); return d; }
#define PINR(arr, n) _Pragma("unroll") for (int i_ = 0; i_ < (n); i_++) asm volatile("" : "+r"((arr)[i_])::"memory")
#define PIN(arr, n) _Pragma("unroll") for (int i_ = 0; i_ < (n); i_++) asm volatile("" : "+f"((arr)[i_])::"memory")

__device__ __forceinline__ uint32_t exp2_pair_fma(float t0, float t1) {
    const uint32_t y = __byte_perm(__float_as_uint(t0), __float_as_uint(t1), 0x6521);
    const uint32_t u = lop_andor(y, 0x007F007Fu, 0x3F803F80u);
    const uint32_t w = bfma2(u, 0x40D140D1u, 0xC11EC11Eu);
    const uint32_t d = bfma2(w, w, 0xC30BC30Bu);
    return y - d + 0x43004300u;
}
__host__ __device__ constexpr bool is_poly(int blk) { return ((blk + 1) * NPOLY) / 16 != (blk * NPOLY) / 16; }
constexpr uint32_t poly_mask() { uint32_t m = 0; for (int b = 0; b < 16; b++) m |= is_poly(b) ? (1u << b) : 0u; return m; }
constexpr uint32_t POLY_MASK = poly_mask();

template <int SUB> __device__ __forceinline__ void exp_fast(const float (&s)[32], uint32_t (&p)[16]) {
#pragma unroll
    for (int b = 0; b < 8; b++) {
        if (is_poly(SUB * 8 + b)) {
            p[2 * b] = exp2_pair_fma(s[4 * b], s[4 * b + 1]);
            p[2 * b + 1] = exp2_pair_fma(s[4 * b + 2], s[4 * b + 3]);
        } else {
            p[2 * b] = pack_bf16(ex2(s[4 * b]), ex2(s[4 * b + 1]));
            p[2 * b + 1] = pack_bf16(ex2(s[4 * b + 2]), ex2(s[4 * b + 3]));
        }
    }
}
__device__ __forceinline__ void issue_qk(float (&s)[32], const uint32_t (&q)[8], uint64_t d) {
    wgmma_n64_rs_z(s, q[0], q[1], q[2], q[3], d);
    wgmma_n64_rs_a(s, q[4], q[5], q[6], q[7], d + 2);
}
__device__ __forceinline__ void issue_pv(float (&o)[16], const uint32_t (&p)[16], uint64_t d) {
#pragma unroll
    for (int kk = 0; kk < 4; kk++) wgmma_n32t_rs_a(o, p[4 * kk], p[4 * kk + 1], p[4 * kk + 2], p[4 * kk + 3], d + 256 + kk * 64);
}
__host__ __device__ constexpr uint32_t slot_off(int sl) { return SM_RING + sl * 16384u; }

template <int G>
__device__ __forceinline__ void p1_mma(float (&acc)[48], uint32_t (&a)[16]) {
    wg_fence();
#pragma unroll
    for (int ks = 0; ks < 4; ks++) {
        const int st = G * 4 + ks;
        const uint64_t db = mkdesc(1024 + SM_W1 + (st < 14 ? st * 1024 : 43008 + (st - 14) * 1024), 14336, 512, 2);
        if (st == 0) wgmma_n96t_rs_z(acc, a[0], a[1], a[2], a[3], db);
        else wgmma_n96t_rs_a(acc, a[4 * ks], a[4 * ks + 1], a[4 * ks + 2], a[4 * ks + 3], db);
    }
    wg_commit();
}
template <bool W = false>
__device__ __forceinline__ void stage4(uint32_t xs, const uint4* p) {
#pragma unroll
    for (int i = 0; i < 4; i++)
        asm volatile("cp.async.cg.shared.global [%0], [%1], 16;" ::"r"(xs + (W ? (i >> 1) * 4096 + (i & 1) * 512 : i * 2048)), "l"(p + i * 128) : "memory");
    asm volatile("cp.async.commit_group;" ::: "memory");
}
__device__ __forceinline__ void stsm4(uint32_t addr, uint32_t a, uint32_t b, uint32_t c, uint32_t d) {
    asm volatile("stmatrix.sync.aligned.m8n8.x4.shared.b16 [%0], {%1,%2,%3,%4};" ::"r"(addr), "r"(a), "r"(b), "r"(c), "r"(d) : "memory");
}

struct Params {
    CUtensorMap tm_w1[2], tm_w2[2];
    const __nv_bfloat16* xin;
    const __nv_bfloat16* wqkv[2];
    __nv_bfloat16* out;
};

__global__ void __launch_bounds__(640, 1) mha4_kernel(const __grid_constant__ Params prm) {
    extern __shared__ __align__(1024) uint8_t smem[];
    constexpr uint32_t sb = 1024;
    constexpr uint32_t bars = sb + SM_BAR;
    if ((uint32_t)__cvta_generic_to_shared(smem) != sb) __trap();
    const int tid = threadIdx.x, warp = __shfl_sync(~0u, tid >> 5, 0), lane = tid & 31;
    const int r = blockIdx.x >> 4, h = blockIdx.x & 15;
    const int b3 = 4 * r + (h >> 3), ks3 = 7 * ((h & 7) >> 1) + 4 * (h & 1);
    const bool odd = h & 1;
    const int wcol = h * DH - (odd ? 4 : 0);
#define BAR(i) (bars + 8 * (i))
    uint32_t xv[8];
#pragma unroll
    for (int i = 0; i < 8; i++) xv[i] = 0u;
    if (warp < 16) {
        const int wg = warp >> 2;
        const uint32_t* xi = (const uint32_t*)(prm.xin + (size_t)((b3 + (wg & 2)) * 64 + (warp & 3) * 16 + (lane >> 2)) * DM + ks3 * 16 + (wg & 1) * 32 + 2 * (lane & 3));
#pragma unroll
        for (int i = 0; i < 4; i++)
            if (i < 2 || !(odd && (wg & 1))) { xv[2 * i] = __ldg(xi + 4 * i); xv[2 * i + 1] = __ldg(xi + 4 * i + 4 * DM); }
    }
    if (tid == 608) asm volatile("prefetch.tensormap [%0];" ::"l"(&prm.tm_w1[0]) : "memory");
    if (tid == 512) {
        mbar_init(BAR(B_W1), 1); mbar_init(BAR(B_W1 + 1), 1); mbar_init(BAR(B_W2), 1);
        mbar_init(BAR(B_P1DONE), 16); mbar_init(BAR(B_P3DONE), 16); mbar_init(BAR(B_DEC), 2); mbar_init(BAR(B_KVPUB), 1);
        for (int i = 0; i < 2; i++) { mbar_init(BAR(B_CS + i), 32); mbar_init(BAR(B_OWN + i), 8); }
        for (int i = 0; i < 5; i++) { mbar_init(BAR(B_FULL + i), 1); mbar_init(BAR(B_ADONE + i), 8); mbar_init(BAR(B_EMPTY + i), 8); }
        *(volatile int*)(smem + SM_DEC + 4) = 0;
        asm volatile("fence.mbarrier_init.release.cluster;" ::: "memory");
    }
    __syncthreads();

    if (warp >= 16) {
        const int w = warp - 16;
        if (w == 3) {
            if (lane == 0) {
                mbar_expect_tx(BAR(B_W1), 43008);
#pragma unroll 1
                for (int s = 0; s < 3; s++) tma2d(sb + SM_W1 + s * 14336, &prm.tm_w1[0], s * DM + wcol, 0, BAR(B_W1));
            }
            __syncwarp();
        }
        if (w < 3) {
            __syncwarp();
            const int col = min(tid - 512, 83), pr = col % 42;
            const uint32_t* wp = (const uint32_t*)(prm.wqkv[col / 42] + (size_t)(r * 56) * (3 * DM) + (pr / 14) * DM + h * DH) + (pr % 14);
            float a0 = 0.f, a1 = 0.f;
            uint32_t wm = 1;
            {
                uint32_t wv[56];
#pragma unroll
                for (int i = 0; i < 56; i++) wv[i] = __ldg(wp + i * (3 * DM / 2));
#pragma unroll
                for (int i = 0; i < 56; i++) { a0 += bf_lo(wv[i]); a1 += bf_hi(wv[i]); wm = max(wm, max(wv[i] & 0x7FFF0000u, (wv[i] << 16) & 0x7FFF0000u)); }
            }
            wm = __reduce_max_sync(~0u, wm);
            if (tid - 512 < 84) {
                uint32_t* cp = &g_csp[h][r][(col / 42) * 96 + (pr / 14) * 32 + (pr % 14) * 2 + (odd ? 4 : 0)];
                asm volatile("st.relaxed.gpu.global.v2.u32 [%0], {%1,%2};" ::"l"(cp), "r"(nz(__float_as_uint(a0))), "r"(nz(__float_as_uint(a1))) : "memory");
            }
            if (lane == 0) st_flag(&g_csp[h][r][192 + w], wm);
            if (tid == 512) st_flag(&g_csp[h][r][195], 1);
            __syncwarp();
        }
        asm volatile("setmaxnreg.dec.sync.aligned.u32 32;");
        if (w < 3 && lane != 0) return;
        if (tid == 544) {
            mbar_expect_tx(BAR(B_W1 + 1), 43008);
#pragma unroll 1
            for (int s = 0; s < 3; s++) tma2d(sb + SM_W1 + 43008 + s * 14336, &prm.tm_w1[0], s * DM + wcol, 224, BAR(B_W1 + 1));
        }
        if (w == 0) {
            uint32_t pass = 0;
#pragma unroll 1
            for (int L = 0; L < NL; L++, pass++) {
                const uint8_t* kv = &g_kv[L & 1][h][0][0];
                const unsigned* fl = &g_kvready[L][h][0];
                mbar_wait(BAR(B_OWN), L & 1);
                bulk_s2g((void*)(kv + r * 32768), sb + slot_off(0), 16384);
                asm volatile("cp.async.bulk.wait_group 0;" ::: "memory");
                st_flag(&g_kvready[L][h][r], 1);
                uint32_t ready = 0;
#pragma unroll 1
                for (int u = 2; u < 16; u++) {
                    const int sl = u % 5, ub = u < 9 ? u - 1 : u, src = (ub & 8) | ((r + ub) & 7);
                    if (!((ready >> src) & 1)) {
                        int tries = 0;
                        do {
                            ready = 0;
#pragma unroll
                            for (int i = 0; i < 4; i++) {
                                uint32_t f[4];
                                ld_ll(f, fl + 4 * i);
#pragma unroll
                                for (int j = 0; j < 4; j++) ready |= f[j] << (4 * i + j);
                            }
                            if (++tries > (1 << 22)) __trap();
                        } while (!((ready >> src) & 1));
                        fence_async_gmem();
                    }
                    if (u == 3) mbar_wait(BAR(B_P1DONE), L & 1);
                    if (u == 6) mbar_wait(BAR(B_KVPUB), L & 1);
                    if (u == 5 || u == 6) mbar_wait(BAR(B_ADONE + sl), stage_par(u, pass) ^ 1);
                    mbar_wait(BAR(B_EMPTY + sl), stage_par(u, pass) ^ 1);
                    mbar_expect_tx(BAR(B_FULL + sl), 16384);
                    bulk_g2s(sb + slot_off(sl), kv + (src & 7) * 32768 + (src >> 3) * 16384, 16384, BAR(B_FULL + sl));
                    *(volatile int*)(smem + SM_DEC + 4) = L * 16 + u;
                }
                mbar_wait(BAR(B_DEC), L & 1);
                if (*(const volatile uint32_t*)(smem + SM_DEC)) {
                    pass++;
#pragma unroll 1
                    for (int u = 0; u < 16; u++) {
                        const int sl = u % 5;
                        mbar_wait(BAR(B_EMPTY + sl), stage_par(u, pass) ^ 1);
                        mbar_expect_tx(BAR(B_FULL + sl), 16384);
                        bulk_g2s(sb + slot_off(sl), kv + u * 16384, 16384, BAR(B_FULL + sl));
                    }
                }
            }
        } else if (w == 1) {
#pragma unroll 1
            for (int L = 0; L < NL; L++) {
                const uint32_t lp = L & 1;
                mbar_wait(BAR(B_P1DONE), lp);
                mbar_expect_tx(BAR(B_W2), 57344);
                if (L < NL - 1) { mbar_expect_tx(BAR(B_W1), 43008); mbar_expect_tx(BAR(B_W1 + 1), 43008); }
#pragma unroll 1
                for (int j = 0; j < 8; j++) {
                    lds_wait_ge(sb + SM_DEC + 4, L * 16 + 4 + (j * 10) / 7);
                    if (j < 2) tma2d(sb + SM_W2 + j * 28672, &prm.tm_w2[lp], ks3 * 16, j * 224, BAR(B_W2));
                    else if (L < NL - 1) tma2d(sb + SM_W1 + (j - 2) * 14336, &prm.tm_w1[lp ^ 1], ((j - 2) % 3) * DM + wcol, ((j - 2) / 3) * 224, BAR(B_W1 + (j - 2) / 3));
                }
            }
        } else if (w == 2) {
#pragma unroll 1
            for (int L = 0; L < NL; L++) {
                mbar_wait(BAR(B_OWN), L & 1);
                mbar_arrive(BAR(B_FULL));
                mbar_wait(BAR(B_OWN + 1), L & 1);
                mbar_arrive(BAR(B_FULL + 1));
                lds_wait_ge(sb + SM_DEC + 4, L * 16 + 2);
                bulk_s2g(&g_kv[L & 1][h][r][16384], sb + slot_off(1), 16384);
                asm volatile("cp.async.bulk.wait_group 0;" ::: "memory");
                st_flag(&g_kvready[L][h][8 + r], 1);
                mbar_arrive(BAR(B_KVPUB));
                mbar_wait(BAR(B_P3DONE), L & 1);
            }
        } else {
#pragma unroll 1
            for (int m = 0; m < 2; m++) {
                const int l = min(lane, 23);
                const bool valid = (l & 7) != (odd ? 0 : 7);
                const uint32_t* cp = &g_csp[h][0][valid ? m * 96 + l * 4 : 192];
                float x[4] = {0.f, 0.f, 0.f, 0.f};
                uint32_t mx = 0;
#pragma unroll 1
                for (int j0 = 0; j0 < 8; j0 += 4) {
                    uint32_t pa[16], mn;
                    int tries = 0;
                    do {
#pragma unroll
                        for (int j = 0; j < 4; j++) ld_ll(pa + 4 * j, cp + (j0 + j) * 200);
                        mn = pa[0];
#pragma unroll
                        for (int j = 1; j < 16; j++) mn = min(mn, pa[j]);
                        if (++tries > (1 << 22)) __trap();
                    } while (__any_sync(~0u, mn == 0));
#pragma unroll
                    for (int j = 0; j < 16; j++) { x[j & 3] += __uint_as_float(pa[j]); mx = max(mx, pa[j]); }
                }
                if (lane < 24) ((float4*)(smem + SM_CS))[m * 24 + lane] = valid ? make_float4(x[0], x[1], x[2], x[3]) : make_float4(__uint_as_float(mx), 0.f, 0.f, 0.f);
                mbar_arrive(BAR(B_CS + m));
                __syncwarp();
            }
#pragma unroll 1
            for (int L = 0; L < NL; L++) {
                const uint32_t lp = L & 1;
                lds_wait_ge(sb + SM_DEC + 4, L * 16 + 6);
                if (lane < 8) {
                    if (lane < 4) bulk_s2g(&g_of[lp ^ 1][4 * r + lane][2 * h][0], sb + SM_TMP, 4096);
                    else bulk_s2g(&g_xf[lp ^ 1][b3 + (lane & 2)][ks3 + 2 * (lane & 1)][0], sb + SM_TMP, (odd && (lane & 1)) ? 2048 : 4096);
                }
#pragma unroll 1
                for (int i = lane; i < 128; i += 32) st_ll(&g_st[lp ^ 1][(b3 + 2 * (i >> 6)) * 64 + (i & 63)][h & 7], 0, 0, 0, 0);
                uint32_t kn[4];
                int tries = 0;
                do {
                    ld_ll(kn, &g_kn[lp][h][lane]);
                    if (++tries > (1 << 22)) __trap();
                } while (__any_sync(~0u, min(min(kn[0], kn[1]), min(kn[2], kn[3])) == 0));
                if (lane < 2) st_flag(&g_kvready[L ^ 2][h][lane * 8 + r], 0);
                if (lane < 4) st_ll(&g_kn[lp ^ 1][h][r * 4 + lane], 0, 0, 0, 0);
                if (L == 1) {
                    st_ll(&g_csp[h][r][lane * 4], 0, 0, 0, 0);
                    if (lane < 18) st_ll(&g_csp[h][r][128 + lane * 4], 0, 0, 0, 0);
                }
                const uint32_t kmax = __reduce_max_sync(~0u, max(max(kn[0], kn[1]), max(kn[2], kn[3])));
                const uint32_t qmax = __reduce_max_sync(~0u, ((const volatile uint32_t*)(smem + SM_NORM))[lane & 15]);
                const uint32_t wmax = ((const volatile uint32_t*)(smem + SM_CS))[odd ? 0 : 28];
                const bool safe = (__uint_as_float(qmax) * __uint_as_float(kmax) <= 9600.f) && (__uint_as_float(wmax) <= 64.f);
                asm volatile("cp.async.bulk.wait_group 0;" ::: "memory");
                __threadfence();
                __syncwarp();
                if (lane == 0) *(volatile uint32_t*)(smem + SM_DEC) = safe ? 0u : 1u;
                if (lane < 2) mbar_arrive(BAR(B_DEC));
                mbar_wait(BAR(B_P3DONE), lp);
            }
        }
    } else {
        const int wg = warp >> 2, strm = warp >> 3, wl = wg & 1;
        const int role = strm ^ 1;
        const bool two = !(odd && wl);
#define COORDS                                                                                   \
        int tid_ = threadIdx.x;                                                                  \
        asm volatile("" : "+r"(tid_));                                                           \
        const int lane = tid_ & 31, g = lane >> 2, c = lane & 3, t128 = tid_ & 127;              \
        const bool spare_hi = !odd && c >= 2, spare_lo = odd && c < 2, spec_hi = !odd && c == 2, spec_lo = odd && c == 0; \
        (void)g; (void)t128; (void)spare_hi; (void)spare_lo; (void)spec_hi; (void)spec_lo;
        float st4[4];
        auto publish_x = [&](int par, bool last, const float (&v)[16]) {
            COORDS
            uint32_t w[8];
#pragma unroll
            for (int i = 0; i < 8; i++) w[i] = pack_bf16(v[2 * i], v[2 * i + 1]);
            if (last) {
                uint32_t* o = (uint32_t*)(prm.out + (size_t)((b3 + 2 * strm) * 64 + (warp & 3) * 16 + g) * DM + ks3 * 16 + wl * 32 + 2 * c);
#pragma unroll
                for (int i = 0; i < 4; i++)
                    if (i < 2 || two) { o[4 * i] = w[2 * i]; o[4 * i + 4 * DM] = w[2 * i + 1]; }
            } else {
                uint4* o = &g_xf[par][b3 + 2 * strm][ks3 + 2 * wl][t128];
                st_ll(o, nz(w[0]), nz(w[1]), nz(w[2]), nz(w[3]));
                if (two) st_ll(o + 128, nz(w[4]), nz(w[5]), nz(w[6]), nz(w[7]));
            }
            st4[0] = st4[1] = st4[2] = st4[3] = 0.f;
#pragma unroll
            for (int i = 0; i < 4; i++) {
                st4[0] += v[4 * i] + v[4 * i + 1]; st4[1] = fmaf(v[4 * i], v[4 * i], fmaf(v[4 * i + 1], v[4 * i + 1], st4[1]));
                st4[2] += v[4 * i + 2] + v[4 * i + 3]; st4[3] = fmaf(v[4 * i + 2], v[4 * i + 2], fmaf(v[4 * i + 3], v[4 * i + 3], st4[3]));
            }
        };
        auto publish_stats = [&](int par) {
            COORDS
#pragma unroll
            for (int o2 = 1; o2 <= 2; o2 <<= 1)
#pragma unroll
                for (int i = 0; i < 4; i++) st4[i] += __shfl_xor_sync(~0u, st4[i], o2);
            if (c < 2) {
                uint2* sp = (uint2*)&g_st[par][(b3 + 2 * strm) * 64 + (warp & 3) * 16 + g + 8 * c][0] + (h & 7) * 2 + wl;
                asm volatile("st.relaxed.gpu.global.v2.u32 [%0], {%1,%2};" ::"l"(sp), "r"(nz(__float_as_uint(c ? st4[2] : st4[0]))), "r"(nz(__float_as_uint(c ? st4[3] : st4[1]))) : "memory");
            }
        };
        {
            float v[16];
#pragma unroll
            for (int i = 0; i < 8; i++) { v[2 * i] = bf_lo(xv[i]); v[2 * i + 1] = bf_hi(xv[i]); }
            publish_x(0, false, v);
            if (tid >= 256) *(uint4*)(smem + SM_TMP + (tid - 256) * 16) = make_uint4(0, 0, 0, 0);
        }
        asm volatile("setmaxnreg.inc.sync.aligned.u32 112;");
        uint32_t pass = 0;
#pragma unroll 1
        for (int L = 0; L < NL; L++, pass++) {
            const uint32_t lp = L & 1;
            uint32_t q[8];
            {
                float acc[48];
                uint32_t sw[16];
                {
                COORDS
                uint32_t a[16], b[16];
                const uint4* xp = &g_xf[lp][4 * r + wg][0][t128];
                const uint32_t xs = sb + slot_off(3) + strm * 16384 + (wl ^ 1) * 8192 + t128 * 16;
                const uint32_t xt = sb + slot_off(0) + role * 16384 + wl * 8192 + (warp & 3) * 1024 + lane * 16;
                mbar_wait(BAR(B_EMPTY + role), stage_par(role, pass) ^ 1);
                ll_fetch4(a, xp);
#pragma unroll
                for (int i = 0; i < 4; i++) ld_ll(b + 4 * i, xp + 512 + i * 128);
                stage4(xs, xp + 2 * 512);
                stage4<true>(xt, xp + 3 * 512);
                mbar_wait(BAR(B_W1), lp);
                p1_mma<0>(acc, a);
                publish_stats(lp);
                ll_settle4(b, xp + 512);
                p1_mma<1>(acc, b);
                wg_wait<1>();
                ll_lds4<1>(a, xs, xp + 2 * 512);
                p1_mma<2>(acc, a);
                stage4(xs, xp + 4 * 512);
                wg_wait<1>();
                ll_lds4w<1>(b, xt, xp + 3 * 512);
                mbar_wait(BAR(B_W1 + 1), lp);
                p1_mma<3>(acc, b);
                stage4<true>(xt, xp + 5 * 512);
                wg_wait<1>();
                ll_lds4<1>(a, xs, xp + 4 * 512);
                p1_mma<4>(acc, a);
                stage4(xs, xp + 6 * 512);
                wg_wait<1>();
                ll_lds4w<1>(b, xt, xp + 5 * 512);
                p1_mma<5>(acc, b);
                {
                    const uint4* sp = &g_st[lp][r * 256 + warp * 16 + g][2 * c];
                    ld_ll(sw, sp); ld_ll(sw + 4, sp + 1); ld_ll(sw + 8, sp + 64); ld_ll(sw + 12, sp + 65);
                }
                wg_wait<1>();
                ll_lds4<0>(a, xs, xp + 6 * 512);
                p1_mma<6>(acc, a);
                }
                COORDS
                float* cs = (float*)(smem + SM_CS);
                if (L < 2) mbar_wait(BAR(B_CS + L), 0);
                float mu0, mu1, rs0, rs1;
                {
                    ll_settle_stats(sw, &g_st[lp][r * 256 + warp * 16 + g][2 * c]);
#define SW(i) __uint_as_float(sw[i])
                    float s0 = (SW(0) + SW(2)) + (SW(4) + SW(6)), q0 = (SW(1) + SW(3)) + (SW(5) + SW(7));
                    float s1 = (SW(8) + SW(10)) + (SW(12) + SW(14)), q1 = (SW(9) + SW(11)) + (SW(13) + SW(15));
#pragma unroll
                    for (int o2 = 1; o2 <= 2; o2 <<= 1) {
                        s0 += __shfl_xor_sync(~0u, s0, o2); q0 += __shfl_xor_sync(~0u, q0, o2);
                        s1 += __shfl_xor_sync(~0u, s1, o2); q1 += __shfl_xor_sync(~0u, q1, o2);
                    }
                    mu0 = s0 * (1.f / DM); mu1 = s1 * (1.f / DM);
                    rs0 = rsqrtf(fmaxf(q0 * (1.f / DM) - mu0 * mu0, 0.f) + 1e-5f);
                    rs1 = rsqrtf(fmaxf(q1 * (1.f / DM) - mu1 * mu1, 0.f) + 1e-5f);
                }
                wg_wait<0>();
                PIN(acc, 48);
                if (lane == 0) mbar_arrive(BAR(B_P1DONE));
                const int srow = (warp & 3) * 16 + (lane & 15 & ~8) + (lane & 8);
                const uint32_t img = sb + slot_off(0) + role * 16384 + wl * 8192 + srow * 64;
                const int blk = wl * 8 + (warp & 3) * 2;
                const uint32_t kspec0 = (POLY_MASK >> blk) & 1 ? 0x3FC43F80u : 0u, kspec1 = (POLY_MASK >> (blk + 1)) & 1 ? 0x3FC43F80u : 0u;
                float nq = 0.f, nk = 0.f;
#pragma unroll
                for (int so = 0; so < 3; so++) {
                    const int sct = so == 2 ? 0 : so + 1;
                    const float f0 = sct == 0 ? rs0 * (0.18898223650461362f * 1.4426950408889634f) : rs0;
                    const float f1 = sct == 0 ? rs1 * (0.18898223650461362f * 1.4426950408889634f) : rs1;
                    float n0 = 0.f, n1 = 0.f;
                    uint32_t w[8];
#pragma unroll
                    for (int i = 0; i < 4; i++) {
                        const float2 cv = *(const float2*)(cs + lp * 96 + sct * 32 + 8 * i + 2 * c);
                        const float* ac = acc + (sct * 4 + i) * 4;
                        float v0 = fmaf(-mu0, cv.x, ac[0]) * f0, v1 = fmaf(-mu0, cv.y, ac[1]) * f0;
                        float v2 = fmaf(-mu1, cv.x, ac[2]) * f1, v3 = fmaf(-mu1, cv.y, ac[3]) * f1;
                        if ((i == 3 && spare_hi) || (i == 0 && spare_lo)) { v0 = v1 = v2 = v3 = 0.f; }
                        if (sct < 2) { n0 = fmaf(v0, v0, fmaf(v1, v1, n0)); n1 = fmaf(v2, v2, fmaf(v3, v3, n1)); }
                        w[2 * i] = pack_bf16(v0, v1); w[2 * i + 1] = pack_bf16(v2, v3);
                        if ((i == 3 && spec_hi) || (i == 0 && spec_lo)) {
                            w[2 * i] = sct == 0 ? 0x3F2843BFu : sct == 1 ? kspec0 : 0x00003F80u;
                            w[2 * i + 1] = sct == 0 ? 0x3F2843BFu : sct == 1 ? kspec1 : 0x00003F80u;
                        }
                    }
                    if (sct == 0) {
#pragma unroll
                        for (int i = 0; i < 8; i++) q[i] = w[i];
                    } else {
                        const int sw = (srow >> 1) & 3, ch = lane >> 4;
                        stsm4(img + (sct - 1) * 4096 + ((ch ^ sw) << 4), w[0], w[1], w[2], w[3]);
                        stsm4(img + (sct - 1) * 4096 + (((2 + ch) ^ sw) << 4), w[4], w[5], w[6], w[7]);
                    }
                    if (sct == 2) {
                        fence_async_smem();
                        __syncwarp();
                        if (lane == 0) mbar_arrive(BAR(B_OWN + role));
                    }
                    if (sct < 2) {
                        n0 += __shfl_xor_sync(~0u, n0, 1); n1 += __shfl_xor_sync(~0u, n1, 1);
                        n0 += __shfl_xor_sync(~0u, n0, 2); n1 += __shfl_xor_sync(~0u, n1, 2);
                        (sct == 0 ? nq : nk) = __uint_as_float(max(__float_as_uint(n0), __float_as_uint(n1)));
                    }
                }
                const uint32_t mq = __reduce_max_sync(~0u, __float_as_uint(nq)), mk = __reduce_max_sync(~0u, __float_as_uint(nk));
                if (lane == 0) {
                    ((uint32_t*)(smem + SM_NORM))[warp] = mq;
                    asm volatile("st.relaxed.gpu.global.u32 [%0], %1;" ::"l"((uint32_t*)&g_kn[lp][h][r * 4] + warp), "r"(nz(mk)) : "memory");
                }
                mbar_wait(BAR(B_OWN), lp);
            }
            const uint32_t done_bar = role ? BAR(B_EMPTY) : BAR(B_ADONE), wait_bar = role ? BAR(B_ADONE) : BAR(B_FULL);
            float o[16];
            {
                float s[32];
                uint32_t p[16], redo = 0;
#pragma unroll
                for (int i = 0; i < 16; i++) o[i] = 0.f;
                PIN(o, 16);
                PINR(q, 8);
                wg_fence();
                const uint64_t ring = mkdesc(sb + SM_RING, 16, 512, 2) + blockIdx.y;
                issue_qk(s, q, ring + (slot_off(0) - SM_RING) / 16);
                wg_commit();
                wg_wait<0>();
                PIN(s, 32);
#pragma unroll
                for (int st = 0; st < 16; st++) {
                    {
                        const int sl = st % 5;
                        const uint64_t rbase = mkdesc(sb + SM_RING, 16, 512, 2) + (blockIdx.y << (st + 1));
                        const uint64_t cur = rbase + sl * 1024, nxt = rbase + ((sl + 1) % 5) * 1024;
                        const uint32_t nbar = (st < 1 ? BAR(B_FULL) : wait_bar) + 8 * ((st + 1) % 5), npar = stage_par(st + 1, pass);
                        const uint32_t landed = st < 15 ? mbar_test(nbar, npar) : 1u;
                        exp_fast<0>(s, p);
                        wg_fence();
                        issue_pv(o, p, cur);
                        issue_qk(s, q, cur + 512);
                        wg_commit();
                        if (!landed) mbar_wait(nbar, npar);
                        if (st == 15) {
                            mbar_wait(BAR(B_DEC), lp);
                            redo = __shfl_sync(~0u, *(const volatile uint32_t*)(smem + SM_DEC), 0);
                        }
                        wg_wait<0>();
                        PIN(s, 32);
                        exp_fast<1>(s, p);
                        wg_fence();
                        issue_pv(o, p, cur + 512);
                        if (st < 15) issue_qk(s, q, nxt);
                        wg_commit();
                        wg_wait<0>();
                        PIN(s, 32);
                        if (lane == 0) mbar_arrive(done_bar + 8 * sl);
                    }
                }
                PIN(o, 16);
                if (redo) {
                    COORDS
                    if (spec_hi) { q[6] = 0u; q[7] = 0u; }
                    if (spec_lo) { q[0] = 0u; q[1] = 0u; }
                    PINR(q, 8);
                    pass++;
                    float m0 = -INFINITY, m1 = -INFINITY;
                    float o2[16], s2[32];
                    uint32_t p2[16];
#pragma unroll
                    for (int i = 0; i < 16; i++) o2[i] = 0.f;
#pragma unroll 1
                    for (int u = 0; u < 32; u++) {
                        const int sl = (u >> 1) % 5;
                        if ((u & 1) == 0) mbar_wait(wait_bar + 8 * sl, stage_par(u >> 1, pass));
                        const uint64_t a = mkdesc(sb + slot_off(sl) + (u & 1) * 8192, 16, 512, 2);
                        PIN(o2, 16);
                        wg_fence();
                        issue_qk(s2, q, a);
                        wg_commit();
                        wg_wait<0>();
                        PIN(s2, 32);
                        float x0 = m0, x1 = m1;
#pragma unroll
                        for (int b = 0; b < 8; b++) { x0 = fmaxf(x0, fmaxf(s2[4 * b], s2[4 * b + 1])); x1 = fmaxf(x1, fmaxf(s2[4 * b + 2], s2[4 * b + 3])); }
                        x0 = fmaxf(x0, __shfl_xor_sync(~0u, x0, 1)); x1 = fmaxf(x1, __shfl_xor_sync(~0u, x1, 1));
                        x0 = fmaxf(x0, __shfl_xor_sync(~0u, x0, 2)); x1 = fmaxf(x1, __shfl_xor_sync(~0u, x1, 2));
                        const float e0 = ex2(m0 - x0), e1 = ex2(m1 - x1);
                        m0 = x0; m1 = x1;
#pragma unroll
                        for (int i = 0; i < 4; i++) { o2[4 * i] *= e0; o2[4 * i + 1] *= e0; o2[4 * i + 2] *= e1; o2[4 * i + 3] *= e1; }
#pragma unroll
                        for (int b = 0; b < 8; b++) {
                            p2[2 * b] = pack_bf16(ex2(s2[4 * b] - m0), ex2(s2[4 * b + 1] - m0));
                            p2[2 * b + 1] = pack_bf16(ex2(s2[4 * b + 2] - m1), ex2(s2[4 * b + 3] - m1));
                        }
                        PIN(o2, 16);
                        wg_fence();
                        issue_pv(o2, p2, a);
                        wg_commit();
                        wg_wait<0>();
                        PIN(o2, 16);
                        if ((u & 1) && lane == 0) mbar_arrive(done_bar + 8 * sl);
                    }
#pragma unroll
                    for (int i = 0; i < 16; i++) o[i] = o2[i];
                }
            }
            {
                COORDS
                const float r0 = __fdividef(1.f, __shfl_sync(~0u, odd ? o[0] : o[12], (lane & ~3) | (odd ? 0 : 2)));
                const float r1 = __fdividef(1.f, __shfl_sync(~0u, odd ? o[2] : o[14], (lane & ~3) | (odd ? 0 : 2)));
                uint32_t w[8];
#pragma unroll
                for (int i = 0; i < 4; i++) {
                    const bool z = (i == 3 && spare_hi) || (i == 0 && spare_lo);
                    w[2 * i] = z ? 1u : nz(pack_bf16(o[4 * i] * r0, o[4 * i + 1] * r0));
                    w[2 * i + 1] = z ? 1u : nz(pack_bf16(o[4 * i + 2] * r1, o[4 * i + 3] * r1));
                }
                uint4* op = &g_of[lp][4 * r + wg][2 * h][t128];
                st_ll(op, w[0], w[1], w[2], w[3]);
                st_ll(op + 128, w[4], w[5], w[6], w[7]);
            }
            {
                COORDS
                uint32_t xo[8] = {0, 0, 0, 0, 0, 0, 0, 0};
                PINR(xo, 8);
                ld_ll(xo, &g_xf[lp][b3 + 2 * strm][ks3 + 2 * wl][t128]);
                if (two) ld_ll(xo + 4, &g_xf[lp][b3 + 2 * strm][ks3 + 2 * wl + 1][t128]);
                uint32_t a[32];
                const uint4* op = &g_of[lp][b3 + 2 * strm][16 * wl][t128];
                poll_nz(op - t128 + (t128 | 31) + (2 * (lane & 7) + 1) * 128);
                ll_fetch8(a, op);
                const uint64_t db = mkdesc(sb + SM_W2, 16, 1024, 1) + (uint32_t)(wl * (28672 / 16));
                float4* part = (float4*)(smem + slot_off(3) + strm * 16384) + t128;
                float v[16];
#pragma unroll
                for (int i = 0; i < 8; i++) { v[2 * i] = bf_lo(xo[i]); v[2 * i + 1] = bf_hi(xo[i]); }
                PIN(v, 16);
                mbar_wait(BAR(B_W2), lp);
                float acc[32];
                auto mma4 = [&](int i0, const uint32_t* ai) {
                    wg_fence();
#pragma unroll
                    for (int j = 0; j < 4; j++) {
                        const int i = i0 + j, row = 56 * (i >> 2) + 24 * ((i >> 1) & 1) + 16 * (i & 1);
                        if (i == 0) wgmma_n64t_rs_z(acc, ai[0], ai[1], ai[2], ai[3], db);
                        else wgmma_n64t_rs_a(acc, ai[4 * j], ai[4 * j + 1], ai[4 * j + 2], ai[4 * j + 3], db + row * 8);
                    }
                    wg_commit();
                };
                mma4(0, a);
                mma4(4, a + 16);
                wg_wait<1>();
#pragma unroll
                for (int i = 0; i < 4; i++) ld_ll(a + 4 * i, op + (8 + i) * 128);
                wg_wait<0>();
#pragma unroll
                for (int i = 0; i < 4; i++) ld_ll(a + 16 + 4 * i, op + (12 + i) * 128);
                ll_settle4(a, op + 1024);
                mma4(8, a);
                ll_settle4(a + 16, op + 1536);
                mma4(12, a + 16);
                mbar_wait(BAR(B_EMPTY + 3 + strm), stage_par(13 + strm, pass));
                wg_wait<0>();
                PIN(acc, 32);
#pragma unroll
                for (int i = 0; i < 4; i++) {
                    part[(wl * 4 + i) * 128] = wl ? make_float4(acc[4 * i], acc[4 * i + 1], acc[4 * i + 2], acc[4 * i + 3])
                                                  : make_float4(acc[16 + 4 * i], acc[17 + 4 * i], acc[18 + 4 * i], acc[19 + 4 * i]);
#pragma unroll
                    for (int j = 0; j < 4; j++) v[4 * i + j] += wl ? acc[16 + 4 * i + j] : acc[4 * i + j];
                }
                bar_sync(2 + strm, 256);
#pragma unroll
                for (int i = 0; i < 4; i++) {
                    const float4 x = part[((wl ^ 1) * 4 + i) * 128];
                    v[4 * i] += x.x; v[4 * i + 1] += x.y; v[4 * i + 2] += x.z; v[4 * i + 3] += x.w;
                    if (i >= 2 && !two) { v[4 * i] = 0.f; v[4 * i + 1] = 0.f; v[4 * i + 2] = 0.f; v[4 * i + 3] = 0.f; }
                }
                PIN(v, 16);
                __syncwarp();
                if (lane == 0) mbar_arrive(BAR(B_P3DONE));
                publish_x(lp ^ 1, L == NL - 1, v);
            }
        }
    }
}

typedef CUresult (*EncodeFn)(CUtensorMap*, CUtensorMapDataType, cuuint32_t, void*, const cuuint64_t*, const cuuint64_t*, const cuuint32_t*,
                             const cuuint32_t*, CUtensorMapInterleave, CUtensorMapSwizzle, CUtensorMapL2promotion, CUtensorMapFloatOOBfill);

void make_map(EncodeFn enc, CUtensorMap* tm, const void* ptr, int cols, int rows, int bc, int br, CUtensorMapSwizzle sw) {
    cuuint64_t gd[2] = {(cuuint64_t)cols, (cuuint64_t)rows};
    cuuint64_t gs[1] = {(cuuint64_t)cols * 2};
    cuuint32_t bd[2] = {(cuuint32_t)bc, (cuuint32_t)br};
    cuuint32_t es[2] = {1, 1};
    enc(tm, CU_TENSOR_MAP_DATA_TYPE_BFLOAT16, 2, const_cast<void*>(ptr), gd, gs, bd, es, CU_TENSOR_MAP_INTERLEAVE_NONE, sw,
        CU_TENSOR_MAP_L2_PROMOTION_L2_128B, CU_TENSOR_MAP_FLOAT_OOB_FILL_NONE);
}

}

extern "C" void kernel_launch(void* const* d_in, const int* in_sizes, int n_in, void* d_out, int out_size) {
    (void)in_sizes; (void)n_in; (void)out_size;
    void* fn = nullptr;
    cudaDriverEntryPointQueryResult qr;
    cudaGetDriverEntryPoint("cuTensorMapEncodeTiled", &fn, cudaEnableDefault, &qr);
    EncodeFn enc = (EncodeFn)fn;
    Params prm;
    make_map(enc, &prm.tm_w1[0], d_in[1], 3 * DM, DM, 32, 224, CU_TENSOR_MAP_SWIZZLE_64B);
    make_map(enc, &prm.tm_w1[1], d_in[4], 3 * DM, DM, 32, 224, CU_TENSOR_MAP_SWIZZLE_64B);
    make_map(enc, &prm.tm_w2[0], d_in[2], DM, DM, 64, 224, CU_TENSOR_MAP_SWIZZLE_128B);
    make_map(enc, &prm.tm_w2[1], d_in[5], DM, DM, 64, 224, CU_TENSOR_MAP_SWIZZLE_128B);
    prm.xin = (const __nv_bfloat16*)d_in[0];
    prm.wqkv[0] = (const __nv_bfloat16*)d_in[1];
    prm.wqkv[1] = (const __nv_bfloat16*)d_in[4];
    prm.out = (__nv_bfloat16*)d_out;
    cudaFuncSetAttribute(mha4_kernel, cudaFuncAttributeMaxDynamicSharedMemorySize, SM_TOTAL);
    mha4_kernel<<<128, 640, SM_TOTAL>>>(prm);
}
```
